```python
import torch

def _softmax(x, axis=-1):
    return torch.softmax(x, dim=axis)

def _gelu(x):
    return torch.nn.functional.gelu(x, approximate='tanh')

def _silu(x):
    return torch.nn.functional.silu(x)

def _sigmoid(x):
    return torch.sigmoid(x)

def _layernorm(x, axis=-1, eps=1e-05):
    m = x.mean(dim=axis, keepdim=True)
    v = x.var(dim=axis, keepdim=True, unbiased=False)
    return (x - m) / torch.sqrt(v + eps)

def _scatter_add(tgt, idx, src, axis=0):
    return tgt.clone().index_add_(axis, idx, src)

def _segment_sum(src, seg, n):
    out = torch.zeros((n,) + src.shape[1:], dtype=src.dtype)
    return out.index_add_(0, seg, src)

def _pad(x, pw):
    flat = tuple((v for pair in reversed(pw) for v in pair))
    return torch.nn.functional.pad(x, flat)
kernel_name = 'adaLN_cond__spectral_fnet__glu_gated_glu__prompt'

def setup_inputs():

    _w = lambda a: (lambda t: t.to(torch.bfloat16) if t.is_floating_point() else t)(torch.as_tensor(a))

    def _A_setup():
        B, S, D = (1, 2048, 512)
        ns = torch.arange(S)[:, None] * torch.arange(S)[None, :]
        nd = torch.arange(D)[:, None] * torch.arange(D)[None, :]
        Ws_re = torch.cos(-2.0 * torch.pi * ns / S).to(float)
        Ws_im = torch.sin(-2.0 * torch.pi * ns / S).to(float)
        Wd_re = torch.cos(-2.0 * torch.pi * nd / D).to(float)
        Wd_im = torch.sin(-2.0 * torch.pi * nd / D).to(float)
        return {'x': _w((lambda *s: torch.randn(*s, dtype=torch.bfloat16) * 0.05)(B, S, D)), 'dft_seq_re': _w(Ws_re), 'dft_seq_im': _w(Ws_im), 'dft_hid_re': _w(Wd_re), 'dft_hid_im': _w(Wd_im)}
    _A_in = _A_setup()

    def _B_setup():
        B, S, D, F = (1, 2048, 512, 1376)
        return {'x': _w((lambda *s: torch.randn(*s, dtype=torch.bfloat16) * 0.05)(B, S, D)), 'w_gate': _w((lambda *s: torch.randn(*s, dtype=torch.bfloat16) * 3.2)(D, F)), 'w_up': _w((lambda *s: torch.randn(*s, dtype=torch.bfloat16) * 3.2)(D, F)), 'w_down': _w((lambda *s: torch.randn(*s, dtype=torch.bfloat16) * 3.2)(F, D))}
    _B_in = _B_setup()
    return {'A_x': _A_in['x'], 'A_dft_seq_re': _A_in['dft_seq_re'], 'A_dft_seq_im': _A_in['dft_seq_im'], 'A_dft_hid_re': _A_in['dft_hid_re'], 'A_dft_hid_im': _A_in['dft_hid_im'], 'B_x': _B_in['x'], 'B_w_gate': _B_in['w_gate'], 'B_w_up': _B_in['w_up'], 'B_w_down': _B_in['w_down'], 'c': _w((lambda *s: torch.randn(*s, dtype=torch.bfloat16) * 0.2)(1, 512) * 8.0), 'w_mod': _w((lambda *s: torch.randn(*s, dtype=torch.bfloat16) * 0.2)(512, 6 * 512) * 512 ** (-0.5) * 8.0)}

def reference(A_x, A_dft_seq_re, A_dft_seq_im, A_dft_hid_re, A_dft_hid_im, B_x, B_w_gate, B_w_up, B_w_down, c, w_mod):

    def _A_ref(x, dft_seq_re, dft_seq_im, dft_hid_re, dft_hid_im):
        a = torch.einsum('bsd,ed->bse', x, dft_hid_re)
        b = torch.einsum('bsd,ed->bse', x, dft_hid_im)
        y = torch.einsum('ts,bse->bte', dft_seq_re, a) - torch.einsum('ts,bse->bte', dft_seq_im, b)
        return y

    def _B_ref(x, w_gate, w_up, w_down):
        g = torch.einsum('bsd,df->bsf', x, w_gate)
        u = torch.einsum('bsd,df->bsf', x, w_up)
        h = _sigmoid(g) * u
        return torch.einsum('bsf,fd->bsd', h, w_down)
    x = A_x
    mod = (_silu(c) @ w_mod).reshape(c.shape[0], 6, 1, -1)
    sa, ca, ga, sb, cb, gb = (mod[:, 0].clone(), mod[:, 1].clone(), mod[:, 2].clone(), mod[:, 3].clone(), mod[:, 4].clone(), mod[:, 5].clone())
    h = _layernorm(x, axis=-1) * (1 + ca) + sa
    x = x + ga * _A_ref(h, A_dft_seq_re, A_dft_seq_im, A_dft_hid_re, A_dft_hid_im)
    h = _layernorm(x, axis=-1) * (1 + cb) + sb
    x = x + gb * _B_ref(h, B_w_gate, B_w_up, B_w_down)
    return x
```

```cpp
#include <cuda_runtime.h>
#include <cuda_bf16.h>
#include <cuda.h>
#include <stdint.h>

namespace {

constexpr int SEQ = 2048, DM = 512, FF = 1376;
constexpr int R = 144;
constexpr int RH = R / 2;
constexpr int NJ = RH / 8;
constexpr int NCL = (SEQ + R - 1) / R;
constexpr int CL = 8;
constexpr int TILE = R * 128;
constexpr int HTILE = RH * 128;
constexpr int BOX = 8192;
constexpr int SLOT = 2 * TILE;
constexpr int NSLOT = 6;
constexpr int NB = 8;
constexpr int STG_TILE = 3;
__host__ __device__ constexpr int phys(int e) { return e == 3 ? 8 : e; }
constexpr int A_OFF = (NB + 1) * TILE;
constexpr int NUNIT = (FF + 63) / 64;
constexpr int MISC = A_OFF + NB * BOX;
static_assert(NSLOT * SLOT <= MISC, "S1 slots");
constexpr int OFF_F1 = 0, OFF_E1 = 48, OFF_FB = 96, OFF_EB = 160, OFF_FA = 224, OFF_EA = 256, OFF_STAGED = 288, OFF_STGFREE = 304,
              OFF_RSBAR = 320, OFF_STATBAR = 328, OFF_MODBAR = 344, OFF_LNBAR = 352, OFF_PUBBAR = 360, OFF_XF = 368, OFF_XE = 376,
              OFF_SGB = 384, OFF_A7B = 392, OFF_BLOB = 400, OFF_WPGO = 448, OFF_CLPUB = 456, OFF_XNLOC = 464, OFF_XNGO = 472, OFF_SLOT0 = 480, OFF_SLOT1 = 488;
constexpr int SMEM_BYTES = MISC + 496;
static_assert(SMEM_BYTES <= 232448, "smem");
constexpr int RS_OFF = A_OFF + (NB - 1) * BOX;
constexpr int SILU_OFF = RS_OFF + 1024;
static_assert(RS_OFF >= NSLOT * SLOT, "scratch");
constexpr int NCTA = NCL * CL;
constexpr int MOD_CTAS = 96;
constexpr int ST_W = 0, ST_X = 4 * RH * 8, ST_F = ST_X + CL * RH * 8;
static_assert(ST_F + RH * 8 <= HTILE, "stats");

struct Params {
  const __nv_bfloat16* x;
  int fused;
  const __nv_bfloat16 *c, *w_mod, *wsp[2], *wdp[2], *wgp, *wup, *wdnp;
  CUtensorMap xn, ws[2], wd[2], wg, wu, wdn, out, xin;
};

__device__ __nv_bfloat16 g_xn[SEQ * DM];
__device__ float g_mod[6 * DM];
__device__ unsigned int g_cnt[64];
__device__ unsigned int g_epoch;
__device__ __align__(1024) uint8_t g_pblob[NCL * 16 * TILE];
__device__ __align__(1024) uint8_t g_hblob[NCL * 8 * TILE];
__device__ __align__(1024) uint8_t g_gblob[NCL * NUNIT * TILE];

__device__ __forceinline__ uint32_t smem_u32(const void* p) { return (uint32_t)__cvta_generic_to_shared(p); }
__device__ __forceinline__ uint32_t launder(uint32_t x) { uint32_t r; asm volatile("mov.b32 %0, %1;" : "=r"(r) : "r"(x)); return r; }
__device__ __forceinline__ void mbar_init(uint32_t bar, uint32_t count) { asm volatile("mbarrier.init.shared::cta.b64 [%0], %1;" :: "r"(bar), "r"(count) : "memory"); }
__device__ __forceinline__ void mbar_expect_tx(uint32_t bar, uint32_t bytes) { asm volatile("mbarrier.arrive.expect_tx.shared::cta.b64 _, [%0], %1;" :: "r"(bar), "r"(bytes) : "memory"); }
__device__ __forceinline__ void mbar_arrive(uint32_t bar) { asm volatile("mbarrier.arrive.shared::cta.b64 _, [%0];" :: "r"(bar) : "memory"); }
__device__ __forceinline__ void mbar_arrive_cluster(uint32_t bar, uint32_t cta) {
  asm volatile("{\n.reg .b32 ra;\nmapa.shared::cluster.u32 ra, %0, %1;\nmbarrier.arrive.shared::cluster.b64 _, [ra];\n}" :: "r"(bar), "r"(cta) : "memory");
}
#define TOK_DECL() asm volatile(".reg .pred tokA, tokB;")
#define TOK_FUNCS(NAME) \
__device__ __forceinline__ void NAME##_test(uint32_t bar, uint32_t parity) { \
  asm volatile("mbarrier.test_wait.parity.shared::cta.b64 " #NAME ", [%0], %1;" :: "r"(bar), "r"(parity) : "memory"); \
} \
__device__ __forceinline__ void NAME##_wait(uint32_t bar, uint32_t parity) { \
  asm volatile("{\n.reg .pred p;\n.reg .u32 n;\n@" #NAME " bra D_%=;\nmov.u32 n, 0;\nW_%=:\nmbarrier.try_wait.parity.shared::cta.b64 p, [%0], %1;\n@p bra D_%=;\n" \
               "add.u32 n, n, 1;\nsetp.lt.u32 p, n, 65536;\n@p bra W_%=;\nD_%=:\n}" :: "r"(bar), "r"(parity) : "memory"); \
}
TOK_FUNCS(tokA)
TOK_FUNCS(tokB)
__device__ __forceinline__ void mbar_wait(uint32_t bar, uint32_t parity) {
  asm volatile("{\n.reg .pred p;\n.reg .u32 n;\nmov.u32 n, 0;\nW_%=:\nmbarrier.try_wait.parity.shared::cta.b64 p, [%0], %1;\n@p bra D_%=;\n"
               "add.u32 n, n, 1;\nsetp.lt.u32 p, n, 65536;\n@p bra W_%=;\nD_%=:\n}" :: "r"(bar), "r"(parity) : "memory");
}
__device__ __forceinline__ void mbar_wait_cl(uint32_t bar, uint32_t parity) {
  asm volatile("{\n.reg .pred p;\n.reg .u32 n;\nmov.u32 n, 0;\nW_%=:\nmbarrier.try_wait.parity.acquire.cluster.shared::cta.b64 p, [%0], %1;\n@p bra D_%=;\n"
               "add.u32 n, n, 1;\nsetp.lt.u32 p, n, 65536;\n@p bra W_%=;\nD_%=:\n}" :: "r"(bar), "r"(parity) : "memory");
}
__device__ __forceinline__ uint32_t mapa(uint32_t addr, uint32_t cta) { uint32_t r; asm volatile("mapa.shared::cluster.u32 %0, %1, %2;" : "=r"(r) : "r"(addr), "r"(cta)); return r; }
__device__ __forceinline__ void mbar_arrive_remote(uint32_t cluster_addr) { asm volatile("mbarrier.arrive.shared::cluster.b64 _, [%0];" :: "r"(cluster_addr) : "memory"); }
__device__ __forceinline__ void st_async_f32(uint32_t addr, float v, uint32_t bar) {
  asm volatile("st.async.weak.shared::cluster.mbarrier::complete_tx::bytes.b32 [%0], %1, [%2];" :: "r"(addr), "r"(__float_as_uint(v)), "r"(bar) : "memory");
}
__device__ __forceinline__ void st_async_f32x2(uint32_t addr, float a, float b, uint32_t bar) {
  asm volatile("st.async.weak.shared::cluster.mbarrier::complete_tx::bytes.v2.b32 [%0], {%1, %2}, [%3];" :: "r"(addr), "r"(__float_as_uint(a)), "r"(__float_as_uint(b)), "r"(bar) : "memory");
}
__device__ __forceinline__ void fence_barrier_init() { asm volatile("fence.mbarrier_init.release.cluster;" ::: "memory"); }
__device__ __forceinline__ void fence_proxy_async() { asm volatile("fence.proxy.async.shared::cta;" ::: "memory"); }
__device__ __forceinline__ void cluster_arrive_relaxed() { asm volatile("barrier.cluster.arrive.relaxed.aligned;" ::: "memory"); }
__device__ __forceinline__ void cluster_wait() { asm volatile("barrier.cluster.wait.acquire.aligned;" ::: "memory"); }
__device__ __forceinline__ uint32_t cluster_ctarank() { uint32_t r; asm volatile("mov.u32 %0, %%cluster_ctarank;" : "=r"(r)); return r; }
__device__ __forceinline__ void named_bar(int id, int n) { asm volatile("bar.sync %0, %1;" :: "r"(id), "r"(n) : "memory"); }
__device__ __forceinline__ void named_arrive(int id, int n) { asm volatile("bar.arrive %0, %1;" :: "r"(id), "r"(n) : "memory"); }
__device__ __forceinline__ void turn_wait(int w) { named_bar(4 + w, 256); }
__device__ __forceinline__ void turn_pass(int w) { named_arrive(5 - w, 256); }

__device__ __forceinline__ void tma_load(uint32_t dst, const CUtensorMap* map, uint32_t bar, int c0, int c1) {
  asm volatile("cp.async.bulk.tensor.2d.shared::cluster.global.mbarrier::complete_tx::bytes [%0], [%1, {%3, %4}], [%2];"
    :: "r"(dst), "l"(map), "r"(bar), "r"(c0), "r"(c1) : "memory");
}
__device__ __forceinline__ void tma_load_mc(uint32_t dst, const CUtensorMap* map, uint32_t bar, int c0, int c1, uint16_t mask) {
  asm volatile("cp.async.bulk.tensor.2d.shared::cluster.global.mbarrier::complete_tx::bytes.multicast::cluster [%0], [%1, {%3, %4}], [%2], %5;"
    :: "r"(dst), "l"(map), "r"(bar), "r"(c0), "r"(c1), "h"(mask) : "memory");
}
__device__ __forceinline__ void tma_prefetch(const CUtensorMap* map, int c0, int c1) {
  asm volatile("cp.async.bulk.prefetch.tensor.2d.L2.global [%0, {%1, %2}];" :: "l"(map), "r"(c0), "r"(c1) : "memory");
}
__device__ __forceinline__ void tma_store(const CUtensorMap* map, uint32_t src, int c0, int c1) {
  asm volatile("cp.async.bulk.tensor.2d.global.shared::cta.bulk_group [%0, {%2, %3}], [%1];" :: "l"(map), "r"(src), "r"(c0), "r"(c1) : "memory");
}
__device__ __forceinline__ void bulk_load_mc(uint32_t dst, const void* src, uint32_t bytes, uint32_t bar, uint16_t mask) {
  asm volatile("cp.async.bulk.shared::cluster.global.mbarrier::complete_tx::bytes.multicast::cluster [%0], [%1], %2, [%3], %4;"
    :: "r"(dst), "l"(src), "r"(bytes), "r"(bar), "h"(mask) : "memory");
}
__device__ __forceinline__ void bulk_store(void* dst, uint32_t src, uint32_t bytes) {
  asm volatile("cp.async.bulk.global.shared::cta.bulk_group [%0], [%1], %2;" :: "l"(dst), "r"(src), "r"(bytes) : "memory");
}
__device__ __forceinline__ void bulk_commit() { asm volatile("cp.async.bulk.commit_group;" ::: "memory"); }
__device__ __forceinline__ void bulk_wait_all() { asm volatile("cp.async.bulk.wait_group 0;" ::: "memory"); }
__device__ __forceinline__ void bulk_wait_read() { asm volatile("cp.async.bulk.wait_group.read 0;" ::: "memory"); }
__device__ __forceinline__ void prefetch_l2(const void* p, uint32_t bytes) { asm volatile("cp.async.bulk.prefetch.L2.global [%0], %1;" :: "l"(p), "r"(bytes) : "memory"); }
__device__ __forceinline__ unsigned int ld_acquire(const unsigned int* p) { unsigned int v; asm volatile("ld.acquire.gpu.global.u32 %0, [%1];" : "=r"(v) : "l"(p) : "memory"); return v; }
__device__ __forceinline__ void red_release(unsigned int* p, unsigned int v) { asm volatile("red.release.gpu.global.add.u32 [%0], %1;" :: "l"(p), "r"(v) : "memory"); }
__device__ __forceinline__ unsigned int ld_relaxed(const unsigned int* p) { unsigned int v; asm volatile("ld.relaxed.gpu.global.u32 %0, [%1];" : "=r"(v) : "l"(p) : "memory"); return v; }
__device__ __forceinline__ void wait_count(const unsigned int* p, unsigned int target) {
  uint32_t n = 0;
#pragma unroll 1
  while ((int)(ld_relaxed(p) - target) < 0) { if (++n > (1u << 15)) break; }
  (void)ld_acquire(p);
}
__device__ __forceinline__ void prefetch_tmap(const CUtensorMap* m) { asm volatile("prefetch.tensormap [%0];" :: "l"(m) : "memory"); }

__device__ __forceinline__ void wgmma_fence() { asm volatile("wgmma.fence.sync.aligned;" ::: "memory"); }
__device__ __forceinline__ void wgmma_commit() { asm volatile("wgmma.commit_group.sync.aligned;" ::: "memory"); }
template <int N> __device__ __forceinline__ void wgmma_wait() { asm volatile("wgmma.wait_group.sync.aligned %0;" :: "n"(N) : "memory"); }
template <int N> __device__ __forceinline__ void fence_regs(float (&d)[N]) {
#pragma unroll
  for (int i = 0; i < N; i++) asm volatile("" : "+f"(d[i]) :: "memory");
}
__device__ __forceinline__ uint32_t desc(uint32_t addr) { return ((addr & 0x3FFFF) >> 4) | 0x10000u; }
__device__ __forceinline__ void wgmma_full_tA(float (&d)[72], uint32_t da, uint32_t db, int scale_d) {
  asm volatile("{\n.reg .pred p;\n.reg .b64 a, b;\nsetp.ne.b32 p, %74, 0;\nmov.b64 a, {%72, %75};\nmov.b64 b, {%73, %75};\n"
    "wgmma.mma_async.sync.aligned.m64n144k16.f32.bf16.bf16 "
    "{%0, %1, %2, %3, %4, %5, %6, %7, %8, %9, %10, %11, %12, %13, %14, %15, %16, %17, %18, %19, %20, %21, %22, %23, %24, %25, %26, %27, %28, %29, %30, %31, %32, %33, %34, %35, %36, %37, %38, %39, %40, %41, %42, %43, %44, %45, %46, %47, %48, %49, %50, %51, %52, %53, %54, %55, %56, %57, %58, %59, %60, %61, %62, %63, %64, %65, %66, %67, %68, %69, %70, %71}, a, b, p, 1, 1, 1, 0;\n}\n"
    : "+f"(d[0]), "+f"(d[1]), "+f"(d[2]), "+f"(d[3]), "+f"(d[4]), "+f"(d[5]), "+f"(d[6]), "+f"(d[7]), "+f"(d[8]), "+f"(d[9]), "+f"(d[10]), "+f"(d[11]), "+f"(d[12]), "+f"(d[13]), "+f"(d[14]), "+f"(d[15]), "+f"(d[16]), "+f"(d[17]), "+f"(d[18]), "+f"(d[19]), "+f"(d[20]), "+f"(d[21]), "+f"(d[22]), "+f"(d[23]), "+f"(d[24]), "+f"(d[25]), "+f"(d[26]), "+f"(d[27]), "+f"(d[28]), "+f"(d[29]), "+f"(d[30]), "+f"(d[31]), "+f"(d[32]), "+f"(d[33]), "+f"(d[34]), "+f"(d[35]), "+f"(d[36]), "+f"(d[37]), "+f"(d[38]), "+f"(d[39]), "+f"(d[40]), "+f"(d[41]), "+f"(d[42]), "+f"(d[43]), "+f"(d[44]), "+f"(d[45]), "+f"(d[46]), "+f"(d[47]), "+f"(d[48]), "+f"(d[49]), "+f"(d[50]), "+f"(d[51]), "+f"(d[52]), "+f"(d[53]), "+f"(d[54]), "+f"(d[55]), "+f"(d[56]), "+f"(d[57]), "+f"(d[58]), "+f"(d[59]), "+f"(d[60]), "+f"(d[61]), "+f"(d[62]), "+f"(d[63]), "+f"(d[64]), "+f"(d[65]), "+f"(d[66]), "+f"(d[67]), "+f"(d[68]), "+f"(d[69]), "+f"(d[70]), "+f"(d[71])
    : "r"(da), "r"(db), "r"(scale_d), "r"(0x40000040u));
}
__device__ __forceinline__ void wgmma_half_kA(float (&d)[36], uint32_t da, uint32_t db, int scale_d) {
  asm volatile("{\n.reg .pred p;\n.reg .b64 a, b;\nsetp.ne.b32 p, %38, 0;\nmov.b64 a, {%36, %39};\nmov.b64 b, {%37, %39};\n"
    "wgmma.mma_async.sync.aligned.m64n72k16.f32.bf16.bf16 "
    "{%0, %1, %2, %3, %4, %5, %6, %7, %8, %9, %10, %11, %12, %13, %14, %15, %16, %17, %18, %19, %20, %21, %22, %23, %24, %25, %26, %27, %28, %29, %30, %31, %32, %33, %34, %35}, a, b, p, 1, 1, 0, 0;\n}\n"
    : "+f"(d[0]), "+f"(d[1]), "+f"(d[2]), "+f"(d[3]), "+f"(d[4]), "+f"(d[5]), "+f"(d[6]), "+f"(d[7]), "+f"(d[8]), "+f"(d[9]), "+f"(d[10]), "+f"(d[11]), "+f"(d[12]), "+f"(d[13]), "+f"(d[14]), "+f"(d[15]), "+f"(d[16]), "+f"(d[17]), "+f"(d[18]), "+f"(d[19]), "+f"(d[20]), "+f"(d[21]), "+f"(d[22]), "+f"(d[23]), "+f"(d[24]), "+f"(d[25]), "+f"(d[26]), "+f"(d[27]), "+f"(d[28]), "+f"(d[29]), "+f"(d[30]), "+f"(d[31]), "+f"(d[32]), "+f"(d[33]), "+f"(d[34]), "+f"(d[35])
    : "r"(da), "r"(db), "r"(scale_d), "r"(0x40000040u));
}
__device__ __forceinline__ void wgmma_half_tA(float (&d)[36], uint32_t da, uint32_t db, int scale_d) {
  asm volatile("{\n.reg .pred p;\n.reg .b64 a, b;\nsetp.ne.b32 p, %38, 0;\nmov.b64 a, {%36, %39};\nmov.b64 b, {%37, %39};\n"
    "wgmma.mma_async.sync.aligned.m64n72k16.f32.bf16.bf16 "
    "{%0, %1, %2, %3, %4, %5, %6, %7, %8, %9, %10, %11, %12, %13, %14, %15, %16, %17, %18, %19, %20, %21, %22, %23, %24, %25, %26, %27, %28, %29, %30, %31, %32, %33, %34, %35}, a, b, p, 1, 1, 1, 0;\n}\n"
    : "+f"(d[0]), "+f"(d[1]), "+f"(d[2]), "+f"(d[3]), "+f"(d[4]), "+f"(d[5]), "+f"(d[6]), "+f"(d[7]), "+f"(d[8]), "+f"(d[9]), "+f"(d[10]), "+f"(d[11]), "+f"(d[12]), "+f"(d[13]), "+f"(d[14]), "+f"(d[15]), "+f"(d[16]), "+f"(d[17]), "+f"(d[18]), "+f"(d[19]), "+f"(d[20]), "+f"(d[21]), "+f"(d[22]), "+f"(d[23]), "+f"(d[24]), "+f"(d[25]), "+f"(d[26]), "+f"(d[27]), "+f"(d[28]), "+f"(d[29]), "+f"(d[30]), "+f"(d[31]), "+f"(d[32]), "+f"(d[33]), "+f"(d[34]), "+f"(d[35])
    : "r"(da), "r"(db), "r"(scale_d), "r"(0x40000040u));
}

__device__ __forceinline__ uint32_t pack_bf16(float lo, float hi) {
  uint32_t r; asm("cvt.rn.bf16x2.f32 %0, %1, %2;" : "=r"(r) : "f"(hi), "f"(lo)); return r;
}
__device__ __forceinline__ void stsm4t(uint32_t addr, uint32_t a, uint32_t b, uint32_t c, uint32_t d) {
  asm volatile("stmatrix.sync.aligned.m8n8.x4.trans.shared.b16 [%0], {%1, %2, %3, %4};" :: "r"(addr), "r"(a), "r"(b), "r"(c), "r"(d) : "memory");
}
__device__ __forceinline__ void stsm2t(uint32_t addr, uint32_t a, uint32_t b) {
  asm volatile("stmatrix.sync.aligned.m8n8.x2.trans.shared.b16 [%0], {%1, %2};" :: "r"(addr), "r"(a), "r"(b) : "memory");
}
__device__ __forceinline__ void ldsm4t(uint32_t addr, uint32_t& a, uint32_t& b, uint32_t& c, uint32_t& d) {
  asm volatile("ldmatrix.sync.aligned.m8n8.x4.trans.shared.b16 {%0, %1, %2, %3}, [%4];" : "=r"(a), "=r"(b), "=r"(c), "=r"(d) : "r"(addr) : "memory");
}
__device__ __forceinline__ uint32_t stsm_addr(uint32_t tile, int row0, int jj, int w4, int lane) {
  const int i = lane >> 3;
  const int t = row0 + 8 * (jj + (i >> 1)) + (lane & 7);
  const int chunk = 2 * w4 + (i & 1);
  return tile + t * 128 + ((chunk ^ (t & 7)) << 4);
}
__device__ __forceinline__ float bf16_bits_to_f32(uint32_t h) { return __uint_as_float(h << 16); }

__device__ __forceinline__ void ln_half(const uint4 (&v4)[4], int row, int l16) {
  float v[32];
#pragma unroll
  for (int c = 0; c < 4; c++) {
    const uint32_t w[4] = {v4[c].x, v4[c].y, v4[c].z, v4[c].w};
#pragma unroll
    for (int i = 0; i < 4; i++) { v[8 * c + 2 * i] = __uint_as_float(w[i] << 16); v[8 * c + 2 * i + 1] = __uint_as_float(w[i] & 0xffff0000u); }
  }
  float s = 0.f;
#pragma unroll
  for (int i = 0; i < 32; i++) s += v[i];
#pragma unroll
  for (int o = 8; o > 0; o >>= 1) s += __shfl_xor_sync(0xffffffffu, s, o);
  const float mean = s * (1.0f / DM);
  float q = 0.f;
#pragma unroll
  for (int i = 0; i < 32; i++) { v[i] -= mean; q += v[i] * v[i]; }
#pragma unroll
  for (int o = 8; o > 0; o >>= 1) q += __shfl_xor_sync(0xffffffffu, q, o);
  const float rstd = rsqrtf(q * (1.0f / DM) + 1e-5f);
  uint4* dst = reinterpret_cast<uint4*>(g_xn + (size_t)row * DM);
#pragma unroll
  for (int c = 0; c < 4; c++) {
    uint4 o;
    o.x = pack_bf16(v[8 * c] * rstd, v[8 * c + 1] * rstd); o.y = pack_bf16(v[8 * c + 2] * rstd, v[8 * c + 3] * rstd);
    o.z = pack_bf16(v[8 * c + 4] * rstd, v[8 * c + 5] * rstd); o.w = pack_bf16(v[8 * c + 6] * rstd, v[8 * c + 7] * rstd);
    dst[c * 16 + l16] = o;
  }
}

__global__ void __launch_bounds__(256) prep_kernel(const __nv_bfloat16* __restrict__ x, const __nv_bfloat16* __restrict__ c,
                                                   const __nv_bfloat16* __restrict__ w_mod) {
  const int warp = threadIdx.x >> 5, lane = threadIdx.x & 31;
  if (blockIdx.x < SEQ / 16) {
    const int row = blockIdx.x * 16 + warp * 2 + (lane >> 4);
    const uint4* src = reinterpret_cast<const uint4*>(x + (size_t)row * DM);
    uint4 v4[4];
#pragma unroll
    for (int c = 0; c < 4; c++) v4[c] = __ldg(src + c * 16 + (lane & 15));
    ln_half(v4, row, lane & 15);
  } else {
    __shared__ float sc[DM];
    __shared__ float2 part[8][32];
    const int b = blockIdx.x - SEQ / 16;
    for (int i = threadIdx.x; i < DM; i += 256) { float cv = __bfloat162float(c[i]); sc[i] = cv / (1.0f + __expf(-cv)); }
    __syncthreads();
    const uint32_t* wp = reinterpret_cast<const uint32_t*>(w_mod + (size_t)(warp * 64) * (6 * DM) + b * 64) + lane;
    float s0 = 0.f, s1 = 0.f;
#pragma unroll 16
    for (int k = 0; k < 64; k++) {
      uint32_t wv = __ldg(wp + (size_t)k * (3 * DM));
      float cv = sc[warp * 64 + k];
      s0 += cv * __uint_as_float(wv << 16); s1 += cv * __uint_as_float(wv & 0xffff0000u);
    }
    part[warp][lane] = make_float2(s0, s1);
    __syncthreads();
    if (warp == 0) {
      float t0 = 0.f, t1 = 0.f;
#pragma unroll
      for (int i = 0; i < 8; i++) { t0 += part[i][lane].x; t1 += part[i][lane].y; }
      g_mod[b * 64 + 2 * lane] = t0; g_mod[b * 64 + 2 * lane + 1] = t1;
    }
  }
}

#define STAGGER 200
__device__ __forceinline__ void stagger(int r) {
  const unsigned int t0 = (unsigned int)clock64();
#pragma unroll 1
  while ((unsigned int)clock64() - t0 < (unsigned)(r * STAGGER)) { }
}
__device__ __forceinline__ void ld16(uint32_t addr, uint32_t (&v)[4]) {
  asm volatile("ld.shared.v4.u32 {%0, %1, %2, %3}, [%4];" : "=r"(v[0]), "=r"(v[1]), "=r"(v[2]), "=r"(v[3]) : "r"(addr));
}
__device__ __forceinline__ float sum16(const uint32_t (&v)[4]) {
  return ((__uint_as_float(v[0] << 16) + __uint_as_float(v[0] & 0xffff0000u)) + (__uint_as_float(v[1] << 16) + __uint_as_float(v[1] & 0xffff0000u)))
       + ((__uint_as_float(v[2] << 16) + __uint_as_float(v[2] & 0xffff0000u)) + (__uint_as_float(v[3] << 16) + __uint_as_float(v[3] & 0xffff0000u)));
}
__device__ __forceinline__ void send_rowsum(float v, uint32_t bars, int row, int p, int lane) {
  v += __shfl_xor_sync(0xffffffffu, v, 1); v += __shfl_xor_sync(0xffffffffu, v, 2); v += __shfl_xor_sync(0xffffffffu, v, 4);
  if ((lane & 7) < 4) {
    const int c = 4 * p + (lane & 3);
    st_async_f32(mapa(bars - (MISC - RS_OFF) + row * 4, c), v, mapa(bars + OFF_RSBAR, c));
  }
}

#define GLU_CH 4
constexpr int GLU_NC = GLU_CH;
__host__ __device__ constexpr int glu_cb(int c) {
  return GLU_CH == 6 ? 6 * c : GLU_CH == 4 ? (c == 0 ? 0 : c == 1 ? 10 : c == 2 ? 20 : c == 3 ? 28 : 36) : 12 * c;
}
template <int S, bool WAIT = true>
__device__ __forceinline__ void glu_step(float (&g)[36], float (&u)[36], uint32_t stg, uint32_t bars, uint32_t& stgfree_ph, int w, int w4, int lane) {
  if constexpr (S >= 1 && S <= GLU_NC) {
#pragma unroll
    for (int i = glu_cb(S - 1); i < glu_cb(S); i += 2) {
      const float a = 1.0f + g[i], b = 1.0f + g[i + 1];
      float rc;
      asm volatile("rcp.approx.ftz.f32 %0, %1;" : "=f"(rc) : "f"(a * b));
      g[i] = rc * b; g[i + 1] = rc * a;
    }
  }
  if constexpr (S < GLU_NC) {
#pragma unroll
    for (int i = glu_cb(S); i < glu_cb(S + 1); i++) asm volatile("ex2.approx.ftz.f32 %0, %1;" : "=f"(g[i]) : "f"(fminf(g[i] * -1.4426950408889634f, 60.0f)));
  }
  if constexpr (S >= 2 && S <= GLU_NC + 1) {
#pragma unroll
    for (int i = glu_cb(S - 2); i < glu_cb(S - 1); i++) u[i] *= g[i];
    if (S == 2 && WAIT) { mbar_wait(bars + OFF_STGFREE + 8 * w, stgfree_ph); stgfree_ph ^= 1; }
    constexpr int B0 = glu_cb(S - 2) / 4;
    constexpr int B1 = glu_cb(S - 1) / 4;
    if constexpr (B1 - B0 >= 2) stsm4t(stsm_addr(stg, w * RH, B0, w4, lane), pack_bf16(u[4 * B0], u[4 * B0 + 1]), pack_bf16(u[4 * B0 + 2], u[4 * B0 + 3]),
                                       pack_bf16(u[4 * B0 + 4], u[4 * B0 + 5]), pack_bf16(u[4 * B0 + 6], u[4 * B0 + 7]));
    if constexpr ((B1 - B0) & 1) stsm2t(stsm_addr(stg, w * RH, B1 - 1, w4, lane & 15), pack_bf16(u[4 * B1 - 4], u[4 * B1 - 3]), pack_bf16(u[4 * B1 - 2], u[4 * B1 - 1]));
    if (S == GLU_NC + 1) { fence_proxy_async(); mbar_arrive(bars + OFF_STAGED + 8 * w); }
  }
}
__device__ __forceinline__ void glu_all(float (&g)[36], float (&u)[36], uint32_t stg, uint32_t bars, uint32_t& ph, int w, int w4, int lane) {
  glu_step<0>(g, u, stg, bars, ph, w, w4, lane); glu_step<1>(g, u, stg, bars, ph, w, w4, lane); glu_step<2>(g, u, stg, bars, ph, w, w4, lane);
  glu_step<3>(g, u, stg, bars, ph, w, w4, lane); glu_step<4>(g, u, stg, bars, ph, w, w4, lane); glu_step<5>(g, u, stg, bars, ph, w, w4, lane);
  glu_step<6>(g, u, stg, bars, ph, w, w4, lane); glu_step<7>(g, u, stg, bars, ph, w, w4, lane);
}
__host__ __device__ constexpr int sl_cb(int c) { return c <= 3 ? 8 * c : c == 4 ? 30 : 36; }
template <int S, int I>
__device__ __forceinline__ void glu_slice(float (&g)[36], float (&u)[36], bool real, uint32_t stg, uint32_t bars, uint32_t& stgfree_ph, int w, int w4, int lane) {
  if constexpr (I < 3 && S >= 1 && S <= 5) {
    constexpr int p0 = I == 0 ? 0 : I + 1, p1 = I == 0 ? 2 : I + 2;
#pragma unroll
    for (int p = p0; p < p1; p++) {
      const int i = sl_cb(S - 1) + 2 * p;
      if (i < sl_cb(S)) {
        const float a = 1.0f + g[i], b = 1.0f + g[i + 1];
        float rc;
        asm volatile("rcp.approx.ftz.f32 %0, %1;" : "=f"(rc) : "f"(a * b));
        g[i] = rc * b; g[i + 1] = rc * a;
      }
    }
  }
  if constexpr ((I == 3 || I == 4) && S <= 4) {
    constexpr int n = (sl_cb(S + 1) - sl_cb(S)) / 2;
#pragma unroll
    for (int i = sl_cb(S) + n * (I - 3); i < sl_cb(S) + n * (I - 2); i++)
      asm volatile("ex2.approx.ftz.f32 %0, %1;" : "=f"(g[i]) : "f"(fminf(g[i] * -1.4426950408889634f, 60.0f)));
  }
  if constexpr (I == 5 && S >= 2 && S <= 6) {
#pragma unroll
    for (int i = sl_cb(S - 2); i < sl_cb(S - 1); i++) u[i] *= g[i];
  }
  if constexpr (I == 6 && S >= 2 && S <= 6) {
    if (real) {
      if (S == 2) { mbar_wait(bars + OFF_STGFREE + 8 * w, stgfree_ph); stgfree_ph ^= 1; }
      constexpr int B0 = sl_cb(S - 2) / 4, B1 = sl_cb(S - 1) / 4;
      if constexpr (B1 - B0 == 2) stsm4t(stsm_addr(stg, w * RH, B0, w4, lane), pack_bf16(u[4 * B0], u[4 * B0 + 1]), pack_bf16(u[4 * B0 + 2], u[4 * B0 + 3]),
                                         pack_bf16(u[4 * B0 + 4], u[4 * B0 + 5]), pack_bf16(u[4 * B0 + 6], u[4 * B0 + 7]));
      else stsm2t(stsm_addr(stg, w * RH, B0, w4, lane & 15), pack_bf16(u[4 * B0], u[4 * B0 + 1]), pack_bf16(u[4 * B0 + 2], u[4 * B0 + 3]));
      if (S == 6) { fence_proxy_async(); mbar_arrive(bars + OFF_STAGED + 8 * w); }
    }
  }
}

template <int KB>
__device__ __forceinline__ void s3_step(float (&g)[36], float (&u)[36], float (&pg)[36], float (&pu)[36], int un, bool glu, bool last,
                                        uint32_t bars, uint32_t rbars, uint32_t dA0, uint32_t dB0, uint32_t stg,
                                        uint32_t& stgfree_ph, int w, int w4, int lane, int tid) {
  constexpr int kb = KB, i = kb & 3;
  {
    if (un == 0) mbar_wait(bars + OFF_FB + 8 * kb, 0);
    tokB_wait(bars + OFF_FA + 8 * i, (kb >> 2) & 1);
    turn_wait(w);
    wgmma_fence();
#define S3_PAIR(K) \
    wgmma_half_tA(g, dA0 + i * (2 * BOX >> 4) + 128 * K, dB0 + phys(kb) * (TILE >> 4) + 2 * K, (kb | K) != 0); \
    glu_slice<KB, 2 * K>(pg, pu, glu, stg, bars, stgfree_ph, w, w4, lane); \
    wgmma_half_tA(u, dA0 + i * (2 * BOX >> 4) + (BOX >> 4) + 128 * K, dB0 + phys(kb) * (TILE >> 4) + 2 * K, (kb | K) != 0); \
    glu_slice<KB, 2 * K + 1>(pg, pu, glu, stg, bars, stgfree_ph, w, w4, lane);
    S3_PAIR(0) S3_PAIR(1) S3_PAIR(2)
    wgmma_half_tA(g, dA0 + i * (2 * BOX >> 4) + 128 * 3, dB0 + phys(kb) * (TILE >> 4) + 2 * 3, 1);
    wgmma_half_tA(u, dA0 + i * (2 * BOX >> 4) + (BOX >> 4) + 128 * 3, dB0 + phys(kb) * (TILE >> 4) + 2 * 3, 1);
    wgmma_commit();
    turn_pass(w);
    tokB_test(bars + OFF_FA + 8 * ((kb + 1) & 3), ((kb + 1) >> 2) & 1);
    glu_slice<KB, 6>(pg, pu, glu, stg, bars, stgfree_ph, w, w4, lane);
    wgmma_wait<0>();
    if (tid == 0) mbar_arrive(bars + OFF_EA + 8 * i);
    if (last && tid < CL) mbar_arrive_remote(rbars + OFF_EB + 8 * kb);
  }
}
__device__ __forceinline__ void s3_unit(float (&g)[36], float (&u)[36], float (&pg)[36], float (&pu)[36], int un, int nunits,
                                        uint32_t sb, uint32_t bars, uint32_t rbars, uint32_t dA0, uint32_t dB0, uint32_t stg,
                                        uint32_t& stgfree_ph, int w, int w4, int lane, int tid) {
  const bool glu = un > 0, last = un == nunits - 1;
  s3_step<0>(g, u, pg, pu, un, glu, last, bars, rbars, dA0, dB0, stg, stgfree_ph, w, w4, lane, tid);
  s3_step<1>(g, u, pg, pu, un, glu, last, bars, rbars, dA0, dB0, stg, stgfree_ph, w, w4, lane, tid);
  s3_step<2>(g, u, pg, pu, un, glu, last, bars, rbars, dA0, dB0, stg, stgfree_ph, w, w4, lane, tid);
  s3_step<3>(g, u, pg, pu, un, glu, last, bars, rbars, dA0, dB0, stg, stgfree_ph, w, w4, lane, tid);
  s3_step<4>(g, u, pg, pu, un, glu, last, bars, rbars, dA0, dB0, stg, stgfree_ph, w, w4, lane, tid);
  s3_step<5>(g, u, pg, pu, un, glu, last, bars, rbars, dA0, dB0, stg, stgfree_ph, w, w4, lane, tid);
  s3_step<6>(g, u, pg, pu, un, glu, last, bars, rbars, dA0, dB0, stg, stgfree_ph, w, w4, lane, tid);
  s3_step<7>(g, u, pg, pu, un, glu, last, bars, rbars, dA0, dB0, stg, stgfree_ph, w, w4, lane, tid);
  fence_regs(g); fence_regs(u);
}

__global__ void __cluster_dims__(CL, 1, 1) __launch_bounds__(384, 1) main_kernel(const __grid_constant__ Params P) {
  extern __shared__ __align__(1024) uint8_t smem[];
  TOK_DECL();
  const uint32_t sb = launder(smem_u32(smem));
  const uint32_t bars = sb + MISC;
  const int r = (int)launder(cluster_ctarank());
  const int q = blockIdx.x / CL;
  const int t0 = q * R;
  const int p = r >> 2, j = r & 3;
  const int wg = __shfl_sync(0xffffffffu, threadIdx.x >> 7, 0);
  const int nunits = (r < NUNIT - 16) ? 3 : 2;

  const int warp_id = threadIdx.x >> 5;
  const bool ln_warp = P.fused && (warp_id < 8 || (warp_id == 10 && blockIdx.x < SEQ / 2 - 8 * NCTA));
  const int ln_row = (warp_id < 8 ? blockIdx.x * 16 + 2 * warp_id : NCTA * 16 + 2 * blockIdx.x) + ((threadIdx.x >> 4) & 1);
  uint4 v4[4];
  if (ln_warp) {
    const uint4* src = reinterpret_cast<const uint4*>(P.x + (size_t)ln_row * DM);
#pragma unroll
    for (int c = 0; c < 4; c++) v4[c] = __ldg(src + c * 16 + (threadIdx.x & 15));
  }
  if (threadIdx.x == 256) {
#pragma unroll
    for (int off = 0; off < SMEM_BYTES - MISC; off += 8) {
      uint32_t cnt = 1;
      if ((off >= OFF_E1 && off < OFF_FB) || (off >= OFF_EB && off < OFF_FA) || off == OFF_XE) cnt = 2 * CL;
      else if ((off >= OFF_EA && off < OFF_STAGED) || off == OFF_A7B) cnt = 2;
      else if (off >= OFF_STAGED && off < OFF_STGFREE) cnt = 128;
      else if (off == OFF_SGB || off == OFF_CLPUB) cnt = CL;
      else if (off == OFF_LNBAR) cnt = blockIdx.x < SEQ / 2 - 8 * NCTA ? 9 : 8;
      mbar_init(bars + off, cnt);
    }
    mbar_expect_tx(bars + OFF_RSBAR, R * 4);
    mbar_expect_tx(bars + OFF_STATBAR, CL * RH * 8);
    mbar_expect_tx(bars + OFF_STATBAR + 8, CL * RH * 8);
    fence_barrier_init();
  }
  __syncthreads();
  cluster_arrive_relaxed();
  if (ln_warp) {
    ln_half(v4, ln_row, threadIdx.x & 15);
    asm volatile("fence.proxy.async.global;" ::: "memory");
    __syncwarp();
    if ((threadIdx.x & 31) == 0) mbar_arrive(bars + OFF_LNBAR);
  }
  cluster_wait();

  if (wg == 2) {
    asm volatile("setmaxnreg.dec.sync.aligned.u32 56;");
    const int warp = (threadIdx.x >> 5) & 3, lane = threadIdx.x & 31;
    if (warp == 0 && lane == 0) {
      prefetch_tmap(&P.xn);
      if (P.fused) {
        mbar_wait(bars + OFF_LNBAR, 0);
        asm volatile("fence.acq_rel.gpu;" ::: "memory");
        mbar_arrive_cluster(bars + OFF_CLPUB, 0);
        mbar_arrive(bars + OFF_PUBBAR);
        if (r == 0) {
          mbar_wait(bars + OFF_CLPUB, 0);
#pragma unroll 1
          for (int i = 0; i < CL; i++) mbar_arrive_cluster(bars + OFF_XNLOC, i);
        }
        mbar_wait(bars + OFF_XNLOC, 0);
      }
      {
        int slot = 0; uint32_t par = 1;
#pragma unroll 1
        for (int it = 0; it < 32; it++) {
          if (it == 2 && P.fused) { mbar_wait(bars + OFF_XNGO, 0); }
          mbar_wait(bars + OFF_E1 + 8 * slot, par);
          mbar_expect_tx(bars + OFF_F1 + 8 * slot, 2 * BOX + TILE);
          tma_load_mc(sb + slot * SLOT + p * BOX, &P.xn, bars + OFF_F1 + 8 * slot, 128 * j + 64 * p, 64 * ((it + 2 * q) & 31), (uint16_t)((1u << j) | (1u << (j + 4))));
          if (++slot == NSLOT) { slot = 0; par ^= 1; }
        }
      }
    } else if (warp == 1 && lane == 0) {
      prefetch_tmap(&P.ws[p]);
      if (P.fused) {
        if (j < 3) {
#pragma unroll 1
          for (int it = 0; it < NSLOT; it++) tma_prefetch(&P.ws[p], 64 * ((it + 2 * q) & 31), t0 + 48 * j);
        }
        mbar_wait(bars + OFF_PUBBAR, 0);
      }
      {
        int slot = 0; uint32_t par = 1;
#pragma unroll 1
        for (int it = 0; it < 32; it++) {
          mbar_wait(bars + OFF_E1 + 8 * slot, par);
          if (j < 3) tma_load_mc(sb + slot * SLOT + 2 * BOX + j * (48 * 128), &P.ws[p], bars + OFF_F1 + 8 * slot, 64 * ((it + 2 * q) & 31), t0 + 48 * j, (uint16_t)(0xFu << (4 * p)));
          if (it >= 8 && it < 30 && (it & 1) == 0) {
            const int un = blockIdx.x + NCTA * ((it - 8) >> 1);
            const char* src = un < 128 ? reinterpret_cast<const char*>(P.wdp[0]) + (size_t)un * 4096
                            : un < 256 ? reinterpret_cast<const char*>(P.wdp[1]) + (size_t)(un - 128) * 4096
                            : un < 600 ? reinterpret_cast<const char*>(P.wgp) + (size_t)(un - 256) * 4096
                            : un < 944 ? reinterpret_cast<const char*>(P.wup) + (size_t)(un - 600) * 4096
                                       : reinterpret_cast<const char*>(P.wdnp) + (size_t)(un - 944) * 4096;
            if (un < 1288) prefetch_l2(src, 4096);
          }
          if (++slot == NSLOT) { slot = 0; par ^= 1; }
        }
      }
      {
        uint8_t* pb = g_pblob + ((size_t)q * 16 + r) * TILE;
        const int e = (r + 4) & 7;
        if (e == 3) mbar_wait(bars + OFF_SGB, 0); else mbar_wait(bars + OFF_E1 + 8 * (e >> 1), e < 4);
        mbar_arrive(bars + OFF_SLOT0);
        mbar_wait(bars + OFF_EB + 8 * e, 0);
        mbar_wait(bars + OFF_BLOB + 8, 0);
        bulk_load_mc(sb + phys(e) * TILE, pb + (size_t)8 * TILE, TILE, bars + OFF_FB + 8 * e, 0xFF);
      }
      mbar_wait(bars + OFF_EB + 8 * 4, 1);
      mbar_expect_tx(bars + OFF_XF, TILE);
      tma_load(sb + 4 * TILE, &P.xin, bars + OFF_XF, 64 * r, t0);
#pragma unroll 1
      for (int i = 0; i < 8; i++) {
        if (i == 4) mbar_wait(bars + OFF_XE, 0); else mbar_wait(bars + OFF_EB + 8 * i, 1);
        mbar_expect_tx(bars + OFF_FB + 8 * i, TILE);
      }
      mbar_arrive(bars + OFF_SLOT1);
#pragma unroll 1
      for (int o = 0; o < nunits; o++) {
        mbar_wait(bars + OFF_EB + 8 * r, o & 1);
        mbar_wait(bars + OFF_BLOB + 8 * (3 + o), 0);
        bulk_load_mc(sb + phys(r) * TILE, g_gblob + ((size_t)q * NUNIT + r + 8 * o) * TILE, TILE, bars + OFF_FB + 8 * r, 0xFF);
      }
    } else if (warp >= 2) {
      const int hw = warp - 2;
      if (P.fused) {
        mbar_wait(bars + OFF_PUBBAR, 0);
        if (lane < 4) {
          const int un = blockIdx.x + NCTA * (4 * hw + lane);
          if (un < 768) prefetch_l2(reinterpret_cast<const char*>(P.w_mod) + (size_t)un * 4096, 4096);
        }
        if (blockIdx.x < MOD_CTAS) {
          float* mp = reinterpret_cast<float*>(smem + SILU_OFF);
#pragma unroll 4
          for (int i = 256 * hw + lane; i < 256 * hw + 256; i += 32) { const float cf = __bfloat162float(P.c[i]); mp[i] = __fdividef(cf, 1.0f + __expf(-cf)); }
          __syncwarp();
          float s[8];
#pragma unroll
          for (int i = 0; i < 8; i++) s[i] = 0.f;
          const uint4* wp = reinterpret_cast<const uint4*>(P.w_mod + (size_t)(256 * hw + (lane >> 2)) * (6 * DM) + blockIdx.x * 32) + (lane & 3);
#pragma unroll 1
          for (int i0 = 0; i0 < 32; i0 += 8) {
            uint4 wv[8];
#pragma unroll
            for (int u = 0; u < 8; u++) wv[u] = __ldg(wp + (size_t)(i0 + u) * (6 * DM));
#pragma unroll
            for (int u = 0; u < 8; u++) {
              const float sl = mp[256 * hw + (lane >> 2) + 8 * (i0 + u)];
              const uint32_t w[4] = {wv[u].x, wv[u].y, wv[u].z, wv[u].w};
#pragma unroll
              for (int h = 0; h < 4; h++) { s[2 * h] += sl * __uint_as_float(w[h] << 16); s[2 * h + 1] += sl * __uint_as_float(w[h] & 0xffff0000u); }
            }
          }
#pragma unroll 1
          for (int o = 4; o <= 16; o <<= 1)
#pragma unroll
            for (int i = 0; i < 8; i++) s[i] += __shfl_xor_sync(0xffffffffu, s[i], o);
          float4* xch = reinterpret_cast<float4*>(smem + SILU_OFF + 2048);
          if (hw == 1 && lane < 4) { xch[2 * lane] = make_float4(s[0], s[1], s[2], s[3]); xch[2 * lane + 1] = make_float4(s[4], s[5], s[6], s[7]); }
          named_bar(3, 64);
          if (hw == 0) {
            if (lane < 4) {
              const float4 a = xch[2 * lane], b = xch[2 * lane + 1];
              float4* dst = reinterpret_cast<float4*>(g_mod + blockIdx.x * 32 + lane * 8);
              dst[0] = make_float4(s[0] + a.x, s[1] + a.y, s[2] + a.z, s[3] + a.w); dst[1] = make_float4(s[4] + b.x, s[5] + b.y, s[6] + b.z, s[7] + b.w);
            }
            __syncwarp();
            if (lane == 0) { red_release(&g_cnt[32], 1u); }
          }
        }
      }
      if (hw == 1) {
        if (lane >= 16 && lane < 22) prefetch_tmap(lane == 16 ? &P.wd[0] : lane == 17 ? &P.wd[1] : lane == 18 ? &P.wg : lane == 19 ? &P.wu : lane == 20 ? &P.wdn : &P.out);
      } else if (lane == 0) {
        if (P.fused) { const unsigned int ep = ld_relaxed(&g_epoch); wait_count(&g_cnt[32], (unsigned)MOD_CTAS * (ep + 1u)); }
        mbar_arrive(bars + OFF_MODBAR);
        const uint32_t stg = sb + STG_TILE * TILE;
        uint8_t* pb = g_pblob + (size_t)q * 16 * TILE;
        mbar_wait(bars + OFF_STAGED, 0);
        bulk_store(pb + (size_t)r * TILE, sb + phys(3) * TILE, HTILE);
        bulk_commit();
        mbar_wait(bars + OFF_STAGED, 1);
        bulk_store(pb + (size_t)r * TILE + HTILE, sb + phys(3) * TILE + HTILE, HTILE);
        bulk_commit();
        bulk_wait_all();
        const unsigned int t_done = (unsigned int)clock64();
        const uint32_t mc_dst = sb + phys((r + 4) & 7) * TILE, mc_bar = bars + OFF_FB + 8 * ((r + 4) & 7);
        if (r == 0) { mbar_wait(bars + OFF_SLOT0, 0); bulk_load_mc(mc_dst, pb, TILE, mc_bar, 0xFF); }
#pragma unroll 1
        for (int i = 0; i < CL; i++) mbar_arrive_cluster(bars + OFF_SGB, (i + 7) & 7);
        if (r != 0) {
          mbar_wait(bars + OFF_SLOT0, 0);
#pragma unroll 1
          while ((unsigned int)clock64() - t_done < (unsigned)(r * STAGGER)) { }
          bulk_load_mc(mc_dst, pb + (size_t)r * TILE, TILE, mc_bar, 0xFF);
        }
        mbar_wait(bars + OFF_STAGED + 8, 0);
        bulk_store(pb + (size_t)(8 + r) * TILE, stg, TILE);
        bulk_commit();
        bulk_wait_all();
        mbar_arrive(bars + OFF_BLOB + 8);
        uint32_t ph0 = 0, ph1 = 1;
#pragma unroll 1
        for (int un = -1; un < nunits; un++) {
          uint8_t* dst = un < 0 ? g_hblob + ((size_t)q * 8 + r) * TILE : g_gblob + ((size_t)q * NUNIT + r + 8 * un) * TILE;
          mbar_wait(bars + OFF_STAGED, ph0);
          bulk_store(dst, stg, HTILE);
          bulk_commit();
          mbar_wait(bars + OFF_STAGED + 8, ph1);
          bulk_store(dst + HTILE, stg + HTILE, HTILE);
          bulk_commit();
          ph0 ^= 1; ph1 ^= 1;
          bulk_wait_all();
          if (un < 0) {
            mbar_wait(bars + OFF_SLOT1, 0);
            stagger(r);
            bulk_load_mc(sb + phys(r) * TILE, dst, TILE, bars + OFF_FB + 8 * r, 0xFF);
          } else mbar_arrive(bars + OFF_BLOB + 8 * (3 + un));
          mbar_arrive(bars + OFF_STGFREE); mbar_arrive(bars + OFF_STGFREE + 8);
        }
      }
    }
    if ((warp == 0 || warp == 3) && lane == 0) {
      const int hp = warp == 3;
      if (!hp) { mbar_wait(bars + OFF_E1 + 8 * 4, 0); mbar_wait(bars + OFF_E1 + 8 * 5, 0); mbar_arrive(bars + OFF_WPGO); }
      else mbar_wait(bars + OFF_WPGO, 0);
#pragma unroll 1
      for (int i = hp; i < 16; i += 2) {
        const int n = i < 3 ? i : i < 7 ? i + 1 : i == 7 ? 3 : i;
        const int e = (n + 4) & 7;
        if (i == 7) mbar_wait(bars + OFF_A7B, 0);
        if (i >= 8) mbar_wait(bars + OFF_EB + 8 * e, 0);
        mbar_expect_tx(bars + OFF_FB + 8 * e, TILE + BOX);
        tma_load(sb + A_OFF + e * BOX, &P.wd[(n >> 2) & 1], bars + OFF_FB + 8 * e, 64 * (2 * (n & 3) + (n >> 3)), 64 * r);
      }
      const int nks = 8 * nunits;
#pragma unroll 1
      for (int ks = hp; ks < nks; ks += 2) {
        const int i = ks & 3;
        if (ks < 4) { mbar_wait(bars + OFF_EB + 16 * i, 1); mbar_wait(bars + OFF_EB + 16 * i + 8, 1); }
        else mbar_wait(bars + OFF_EA + 8 * i, ((ks >> 2) + 1) & 1);
        mbar_expect_tx(bars + OFF_FA + 8 * i, 2 * BOX);
        const int f0 = 64 * (r + 8 * (ks >> 3)), e0 = 64 * (ks & 7);
        tma_load(sb + A_OFF + 2 * i * BOX, &P.wg, bars + OFF_FA + 8 * i, f0, e0);
        tma_load(sb + A_OFF + (2 * i + 1) * BOX, &P.wu, bars + OFF_FA + 8 * i, f0, e0);
      }
#pragma unroll 1
      for (int kb = hp; kb < NUNIT; kb += 2) {
        const int e = kb & 7;
        if (kb < 8) mbar_wait(bars + OFF_EA + 8 * (e >> 1), 1);
        else mbar_wait(bars + OFF_EB + 8 * e, (kb >> 3) & 1);
        mbar_expect_tx(bars + OFF_FB + 8 * e, TILE + BOX);
        tma_load(sb + A_OFF + e * BOX, &P.wdn, bars + OFF_FB + 8 * e, 64 * r, 64 * kb);
        if (kb < 8) mbar_wait(bars + OFF_EB + 8 * e, 0);
      }
    }
    __syncwarp();
    cluster_arrive_relaxed(); cluster_wait();
  } else {
    asm volatile("setmaxnreg.inc.sync.aligned.u32 224;");
    const int w = wg;
    const int tid = threadIdx.x & 127, w4 = tid >> 5, lane = tid & 31;
    const int rowo = 16 * w4 + (lane >> 2);
    const uint32_t rbars = mapa(bars, tid & 7);
    const uint32_t dA0 = desc(sb + A_OFF), dB0 = desc(sb + w * HTILE);
    {
      float acc[72];
      if (P.fused && r == 0 && threadIdx.x == 128) {
        const unsigned int ep = ld_relaxed(&g_epoch);
        mbar_wait(bars + OFF_CLPUB, 0);
        asm volatile("red.relaxed.gpu.global.add.u32 [%0], %1;" :: "l"(&g_cnt[0]), "r"(1u) : "memory");
        wait_count(&g_cnt[0], (unsigned)NCL * (ep + 1u));
#pragma unroll 1
        for (int i = 0; i < CL; i++) mbar_arrive_cluster(bars + OFF_XNGO, i);
      }
      __syncwarp();
      if (w == 1) turn_pass(1);
      tokA_test(bars + OFF_F1, 0);
      float rsum = 0.f, rsum2 = 0.f, scA = 0.f, scB = 0.f, shA = 0.f, shB = 0.f;
      const uint32_t roff = sb + 2 * BOX + (36 * j) * 128 + threadIdx.x * 16;
      const uint32_t d1a = desc(sb + w * BOX), d1b = desc(sb + 2 * BOX);
#pragma unroll 1
      for (int o = 0; o < 6; o++) {
        const uint32_t par = o & 1;
#pragma unroll
        for (int sl = 0; sl < NSLOT; sl++) {
          if (sl == 2 && o == 5) break;
          tokA_wait(bars + OFF_F1 + 8 * sl, par);
          uint32_t rv[4], rx[4];
          ld16(roff + sl * SLOT, rv);
          if (threadIdx.x < 32) ld16(roff + sl * SLOT + 4096, rx);
          turn_wait(w);
          wgmma_fence();
#pragma unroll
          for (int k = 0; k < 4; k++) wgmma_full_tA(acc, d1a + sl * (SLOT >> 4) + 128 * k, d1b + sl * (SLOT >> 4) + 2 * k, (sl | k) != 0 || o != 0);
          wgmma_commit();
          turn_pass(w);
          tokA_test(bars + OFF_F1 + 8 * ((sl + 1) % NSLOT), sl == NSLOT - 1 ? par ^ 1 : par);
          asm volatile("" : "+r"(rv[0]), "+r"(rv[1]), "+r"(rv[2]), "+r"(rv[3]));
          rsum += sum16(rv);
          if (threadIdx.x < 32) { asm volatile("" : "+r"(rx[0]), "+r"(rx[1]), "+r"(rx[2]), "+r"(rx[3])); rsum2 += sum16(rx); }
          if (sl == 0 && o == 4) {
            mbar_wait(bars + OFF_MODBAR, 0);
            const float* m = g_mod + 128 * j + 64 * w + rowo;
            shA = __ldcg(m); shB = __ldcg(m + 8); scA = __ldcg(m + DM); scB = __ldcg(m + DM + 8);
          }
          wgmma_wait<1>();
          if ((sl > 0 || o > 0) && tid < CL) mbar_arrive_remote(rbars + OFF_E1 + 8 * ((sl + NSLOT - 1) % NSLOT));
        }
      }
      const uint32_t prevb = 8 * 1;
      send_rowsum(rsum, bars, 36 * j + (threadIdx.x >> 3), p, lane);
      if (threadIdx.x < 32) send_rowsum(rsum2, bars, 36 * j + 32 + (lane >> 3), p, lane);
      wgmma_wait<0>();
      if (tid < CL) mbar_arrive_remote(rbars + OFF_E1 + prevb);
      fence_regs(acc);
      { const float sgn = p ? -1.0f : 1.0f; scA = sgn * (1.0f + scA); scB = sgn * (1.0f + scB); shA *= sgn; shB *= sgn; }
      mbar_wait_cl(bars + OFF_RSBAR, 0);
      mbar_wait(bars + OFF_E1 + (w ? 8 * 1 : 8 * 4), w);
      const uint32_t tile = sb + (w ? STG_TILE : phys(3)) * TILE;
      const float* rs = reinterpret_cast<const float*>(smem + RS_OFF);
#pragma unroll
      for (int jj = 0; jj < 18; jj += 2) {
        uint32_t pk[4];
#pragma unroll
        for (int h = 0; h < 2; h++) {
          const float2 rv = *reinterpret_cast<const float2*>(rs + 8 * (jj + h) + 2 * (lane & 3));
          const int i = 4 * (jj + h);
          pk[2 * h] = pack_bf16(acc[i] * scA + rv.x * shA, acc[i + 1] * scA + rv.y * shA);
          pk[2 * h + 1] = pack_bf16(acc[i + 2] * scB + rv.x * shB, acc[i + 3] * scB + rv.y * shB);
        }
        stsm4t(stsm_addr(tile, 0, jj, w4, lane), pk[0], pk[1], pk[2], pk[3]);
        if (jj == 8 && w == 0) { fence_proxy_async(); mbar_arrive(bars + OFF_STAGED); }
      }
      fence_proxy_async();
      mbar_arrive(bars + OFF_STAGED + 8 * w);
      named_bar(1 + w, 128);
      if (tid == 0) mbar_arrive(bars + OFF_A7B);
    }
    uint32_t x1p[18];
    uint32_t stgfree_ph = 0;
    const uint32_t stg = sb + STG_TILE * TILE;
    {
      float x1[36];
      const float* m = g_mod + 64 * r + rowo;
      const float gaA = __ldcg(m + 2 * DM), gaB = __ldcg(m + 2 * DM + 8), sbA = __ldcg(m + 3 * DM), sbB = __ldcg(m + 3 * DM + 8);
      const float cbA = 1.0f + __ldcg(m + 4 * DM), cbB = 1.0f + __ldcg(m + 4 * DM + 8);
      tokA_test(bars + OFF_FB + 8 * 4, 0);
#pragma unroll 1
      for (int o = 0; o < 2; o++) {
#pragma unroll
        for (int i = 0; i < 8; i++) {
          const int e = (i + 4) & 7;
          tokA_wait(bars + OFF_FB + 8 * e, o);
          wgmma_fence();
#pragma unroll
          for (int k = 0; k < 4; k++) wgmma_half_kA(x1, dA0 + e * (BOX >> 4) + 2 * k, dB0 + phys(e) * (TILE >> 4) + 2 * k, (i | k) != 0 || o != 0);
          wgmma_commit();
          tokA_test(bars + OFF_FB + 8 * ((e + 1) & 7), i == 7 ? o ^ 1 : o);
          wgmma_wait<1>();
          if ((i > 0 || o > 0) && tid < CL) mbar_arrive_remote(rbars + OFF_EB + 8 * ((e + 7) & 7));
        }
      }
      wgmma_wait<0>();
      if (tid < CL) mbar_arrive_remote(rbars + OFF_EB + 8 * 3);
      tokB_test(bars + OFF_FA, 0);
      fence_regs(x1);
      mbar_wait(bars + OFF_XF, 0);
      {
        uint32_t xr[20];
        const uint32_t xt = sb + 4 * TILE;
#pragma unroll
        for (int jj = 0; jj < 10; jj += 2) ldsm4t(stsm_addr(xt, w * RH, jj, w4, jj == 8 ? (lane & 15) : lane), xr[2 * jj], xr[2 * jj + 1], xr[2 * jj + 2], xr[2 * jj + 3]);
        if (tid < CL) mbar_arrive_remote(rbars + OFF_XE);
#pragma unroll
        for (int jj = 0; jj < NJ; jj++) {
          x1[4 * jj] = bf16_bits_to_f32(xr[2 * jj] & 0xffffu) + gaA * x1[4 * jj];
          x1[4 * jj + 1] = __uint_as_float(xr[2 * jj] & 0xffff0000u) + gaA * x1[4 * jj + 1];
          x1[4 * jj + 2] = bf16_bits_to_f32(xr[2 * jj + 1] & 0xffffu) + gaB * x1[4 * jj + 2];
          x1[4 * jj + 3] = __uint_as_float(xr[2 * jj + 1] & 0xffff0000u) + gaB * x1[4 * jj + 3];
        }
      }
      float m3[3], q3[3];
      {
        float m[18], qq[18];
#pragma unroll
        for (int jj = 0; jj < NJ; jj++)
#pragma unroll
          for (int c = 0; c < 2; c++) {
            const float a = x1[4 * jj + c], b = x1[4 * jj + 2 + c];
            m[2 * jj + c] = a + b; qq[2 * jj + c] = a * a + b * b;
          }
        float m1[10], q1[10];
        {
          const bool hi = lane & 16;
#pragma unroll
          for (int k = 0; k < 9; k++) {
            m1[k] = (hi ? m[9 + k] : m[k]) + __shfl_xor_sync(0xffffffffu, hi ? m[k] : m[9 + k], 16);
            q1[k] = (hi ? qq[9 + k] : qq[k]) + __shfl_xor_sync(0xffffffffu, hi ? qq[k] : qq[9 + k], 16);
          }
          m1[9] = 0.f; q1[9] = 0.f;
        }
        float m2[6], q2[6];
        {
          const bool hi = lane & 8;
#pragma unroll
          for (int k = 0; k < 5; k++) {
            m2[k] = (hi ? m1[5 + k] : m1[k]) + __shfl_xor_sync(0xffffffffu, hi ? m1[k] : m1[5 + k], 8);
            q2[k] = (hi ? q1[5 + k] : q1[k]) + __shfl_xor_sync(0xffffffffu, hi ? q1[k] : q1[5 + k], 8);
          }
          m2[5] = 0.f; q2[5] = 0.f;
        }
        {
          const bool hi = lane & 4;
#pragma unroll
          for (int k = 0; k < 3; k++) {
            m3[k] = (hi ? m2[3 + k] : m2[k]) + __shfl_xor_sync(0xffffffffu, hi ? m2[k] : m2[3 + k], 4);
            q3[k] = (hi ? q2[3 + k] : q2[k]) + __shfl_xor_sync(0xffffffffu, hi ? q2[k] : q2[3 + k], 4);
          }
        }
      }
      uint8_t* half = smem + STG_TILE * TILE + w * HTILE;
      float2* wstat = reinterpret_cast<float2*>(half + ST_W);
#pragma unroll
      for (int k = 0; k < 3; k++) {
        const int i5 = ((lane & 4) ? 3 : 0) + k;
        const int i9 = ((lane & 8) ? 5 : 0) + i5;
        const int i18 = ((lane & 16) ? 9 : 0) + i9;
        if (i5 < 5 && i9 < 9) wstat[w4 * RH + 8 * (i18 >> 1) + 2 * (lane & 3) + (i18 & 1)] = make_float2(m3[k], q3[k]);
      }
      named_bar(1 + w, 128);
      float2* fin = reinterpret_cast<float2*>(half + ST_F);
      if (tid < RH) {
        const float2 a = wstat[tid], b = wstat[RH + tid], c = wstat[2 * RH + tid], d = wstat[3 * RH + tid];
        const float s1 = (a.x + b.x) + (c.x + d.x), s2 = (a.y + b.y) + (c.y + d.y);
        const uint32_t dst = stg + w * HTILE + ST_X + (r * RH + tid) * 8;
#pragma unroll
        for (int c2 = 0; c2 < CL; c2++) st_async_f32x2(mapa(dst, c2), s1, s2, mapa(bars + OFF_STATBAR + 8 * w, c2));
        mbar_wait_cl(bars + OFF_STATBAR + 8 * w, 0);
        const float2* st = reinterpret_cast<const float2*>(half + ST_X) + tid;
        float t1 = 0.f, t2 = 0.f;
#pragma unroll
        for (int c2 = 0; c2 < CL; c2++) { const float2 v = st[c2 * RH]; t1 += v.x; t2 += v.y; }
        const float mu = t1 * (1.0f / DM);
        const float rstd = rsqrtf(fmaxf(t2 * (1.0f / DM) - mu * mu, 0.f) + 1e-5f);
        fin[tid] = make_float2(rstd, -mu * rstd);
      }
      named_bar(1 + w, 128);
      {
        uint32_t pk[2 * NJ];
#pragma unroll
        for (int jj = 0; jj < NJ; jj++) {
          const float4 f = *reinterpret_cast<const float4*>(fin + 8 * jj + 2 * (lane & 3));
          pk[2 * jj] = pack_bf16(fmaf(fmaf(x1[4 * jj], f.x, f.y), cbA, sbA), fmaf(fmaf(x1[4 * jj + 1], f.z, f.w), cbA, sbA));
          pk[2 * jj + 1] = pack_bf16(fmaf(fmaf(x1[4 * jj + 2], f.x, f.y), cbB, sbB), fmaf(fmaf(x1[4 * jj + 3], f.z, f.w), cbB, sbB));
          x1p[2 * jj] = pack_bf16(x1[4 * jj], x1[4 * jj + 1]); x1p[2 * jj + 1] = pack_bf16(x1[4 * jj + 2], x1[4 * jj + 3]);
        }
        named_bar(1 + w, 128);
#pragma unroll
        for (int jj = 0; jj < 8; jj += 2) stsm4t(stsm_addr(stg, w * RH, jj, w4, lane), pk[2 * jj], pk[2 * jj + 1], pk[2 * jj + 2], pk[2 * jj + 3]);
        stsm2t(stsm_addr(stg, w * RH, 8, w4, lane & 15), pk[16], pk[17]);
        fence_proxy_async();
        mbar_arrive(bars + OFF_STAGED + 8 * w);
      }
    }
    float pg[36], pu[36];
    {
      float g[36], u[36];
#pragma unroll 1
      for (int un = 0; un < nunits; un++) {
        s3_unit(g, u, pg, pu, un, nunits, sb, bars, rbars, dA0, dB0, stg, stgfree_ph, w, w4, lane, tid);
#pragma unroll
        for (int i = 0; i < 36; i++) {
          asm volatile("mov.f32 %0, %1;" : "=f"(pg[i]) : "f"(g[i]));
          asm volatile("mov.f32 %0, %1;" : "=f"(pu[i]) : "f"(u[i]));
        }
      }
      glu_all(pg, pu, stg, bars, stgfree_ph, w, w4, lane);
    }
    {
      float acc[36];
      const float gbA = __ldcg(g_mod + 5 * DM + 64 * r + rowo), gbB = __ldcg(g_mod + 5 * DM + 64 * r + rowo + 8);
      tokA_test(bars + OFF_FB, 1);
#pragma unroll 1
      for (int o = 0; o < 3; o++) {
        const uint32_t par = (o + 1) & 1;
#pragma unroll
        for (int e = 0; e < 8; e++) {
          if (e == NUNIT - 16 && o == 2) break;
          tokA_wait(bars + OFF_FB + 8 * e, par);
          wgmma_fence();
#pragma unroll
          for (int k = 0; k < 4; k++) wgmma_half_tA(acc, dA0 + e * (BOX >> 4) + 128 * k, dB0 + phys(e) * (TILE >> 4) + 2 * k, (e | k) != 0 || o != 0);
          wgmma_commit();
          tokA_test(bars + OFF_FB + 8 * ((e + 1) & 7), e == 7 ? par ^ 1 : par);
          wgmma_wait<1>();
          if ((e > 0 || o > 0) && tid < CL) mbar_arrive_remote(rbars + OFF_EB + 8 * ((e + 7) & 7));
        }
      }
      wgmma_wait<0>();
      fence_regs(acc);
      mbar_wait(bars + OFF_STGFREE + 8 * w, stgfree_ph);
      const uint32_t ostg = stg;
      uint32_t pk[2 * NJ];
#pragma unroll
      for (int jj = 0; jj < NJ; jj++) {
        pk[2 * jj] = pack_bf16(__uint_as_float(x1p[2 * jj] << 16) + gbA * acc[4 * jj], __uint_as_float(x1p[2 * jj] & 0xffff0000u) + gbA * acc[4 * jj + 1]);
        pk[2 * jj + 1] = pack_bf16(__uint_as_float(x1p[2 * jj + 1] << 16) + gbB * acc[4 * jj + 2], __uint_as_float(x1p[2 * jj + 1] & 0xffff0000u) + gbB * acc[4 * jj + 3]);
      }
#pragma unroll
      for (int jj = 0; jj < 8; jj += 2) stsm4t(stsm_addr(ostg, w * RH, jj, w4, lane), pk[2 * jj], pk[2 * jj + 1], pk[2 * jj + 2], pk[2 * jj + 3]);
      stsm2t(stsm_addr(ostg, w * RH, 8, w4, lane & 15), pk[16], pk[17]);
      fence_proxy_async();
      named_bar(1 + w, 128);
      if (tid == 0) {
        tma_store(&P.out, ostg + w * HTILE, 64 * r, t0 + w * RH);
        bulk_commit();
        bulk_wait_read();
      }
    }
    if (w == 0) turn_wait(0);
    if (P.fused && blockIdx.x == 0 && threadIdx.x == 0) *reinterpret_cast<volatile unsigned int*>(&g_epoch) = ld_relaxed(&g_epoch) + 1u;
    cluster_arrive_relaxed(); cluster_wait();
  }
}

typedef CUresult (*EncodeFn)(CUtensorMap*, CUtensorMapDataType, cuuint32_t, void*, const cuuint64_t*, const cuuint64_t*, const cuuint32_t*,
                             const cuuint32_t*, CUtensorMapInterleave, CUtensorMapSwizzle, CUtensorMapL2promotion, CUtensorMapFloatOOBfill);

void make_map(EncodeFn enc, CUtensorMap* m, const void* ptr, uint64_t cols, uint64_t rows, uint32_t box_cols, uint32_t box_rows,
              CUtensorMapL2promotion prom = CU_TENSOR_MAP_L2_PROMOTION_L2_128B) {
  cuuint64_t dims[2] = {cols, rows};
  cuuint64_t strides[1] = {cols * 2};
  cuuint32_t box[2] = {box_cols, box_rows};
  cuuint32_t es[2] = {1, 1};
  enc(m, CU_TENSOR_MAP_DATA_TYPE_BFLOAT16, 2, const_cast<void*>(ptr), dims, strides, box, es, CU_TENSOR_MAP_INTERLEAVE_NONE,
      CU_TENSOR_MAP_SWIZZLE_128B, prom, CU_TENSOR_MAP_FLOAT_OOB_FILL_NONE);
}

}

extern "C" void kernel_launch(void* const* d_in, const int* in_sizes, int n_in, void* d_out, int out_size) {
  (void)in_sizes; (void)n_in; (void)out_size;
  static Params P;
  static const void* cached[12] = {};
  static bool init = false;
  bool same = init;
  for (int i = 0; i < 11 && same; i++) same = (cached[i] == d_in[i]);
  same = same && cached[11] == d_out;
  if (!same) {
    void* fn = nullptr; cudaDriverEntryPointQueryResult qr;
    cudaGetDriverEntryPoint("cuTensorMapEncodeTiled", &fn, cudaEnableDefault, &qr);
    EncodeFn enc = (EncodeFn)fn;
    void* xn = nullptr; cudaGetSymbolAddress(&xn, g_xn);
    make_map(enc, &P.xn, xn, DM, SEQ, 64, 64);
    make_map(enc, &P.ws[0], d_in[1], SEQ, SEQ, 64, 48);
    make_map(enc, &P.ws[1], d_in[2], SEQ, SEQ, 64, 48);
    make_map(enc, &P.wd[0], d_in[3], DM, DM, 64, 64);
    make_map(enc, &P.wd[1], d_in[4], DM, DM, 64, 64);
    make_map(enc, &P.wg, d_in[6], FF, DM, 64, 64);
    make_map(enc, &P.wu, d_in[7], FF, DM, 64, 64);
    make_map(enc, &P.wdn, d_in[8], DM, FF, 64, 64);
    make_map(enc, &P.out, d_out, DM, SEQ, 64, RH);
    make_map(enc, &P.xin, d_in[0], DM, SEQ, 64, R);
    P.x = (const __nv_bfloat16*)d_in[0]; P.c = (const __nv_bfloat16*)d_in[9]; P.w_mod = (const __nv_bfloat16*)d_in[10];
    P.wsp[0] = (const __nv_bfloat16*)d_in[1]; P.wsp[1] = (const __nv_bfloat16*)d_in[2];
    P.wdp[0] = (const __nv_bfloat16*)d_in[3]; P.wdp[1] = (const __nv_bfloat16*)d_in[4];
    P.wgp = (const __nv_bfloat16*)d_in[6]; P.wup = (const __nv_bfloat16*)d_in[7]; P.wdnp = (const __nv_bfloat16*)d_in[8];
    cudaFuncSetAttribute(main_kernel, cudaFuncAttributeMaxDynamicSharedMemorySize, SMEM_BYTES);
    {
      cudaLaunchConfig_t cfg = {};
      cfg.gridDim = dim3(NCL * CL); cfg.blockDim = dim3(384); cfg.dynamicSmemBytes = SMEM_BYTES;
      cudaLaunchAttribute at[1];
      at[0].id = cudaLaunchAttributeClusterDimension; at[0].val.clusterDim.x = CL; at[0].val.clusterDim.y = 1; at[0].val.clusterDim.z = 1;
      cfg.attrs = at; cfg.numAttrs = 1;
      int ncl = 0;
      P.fused = (cudaOccupancyMaxActiveClusters(&ncl, main_kernel, &cfg) == cudaSuccess && ncl >= NCL) ? 1 : 0;
    }
    for (int i = 0; i < 11; i++) cached[i] = d_in[i];
    cached[11] = d_out;
    init = true;
  }
  cudaStream_t st = cudaStreamPerThread;
  if (!P.fused) prep_kernel<<<SEQ / 16 + 48, 256, 0, st>>>((const __nv_bfloat16*)d_in[0], (const __nv_bfloat16*)d_in[9], (const __nv_bfloat16*)d_in[10]);
  main_kernel<<<NCL * CL, 384, SMEM_BYTES, st>>>(P);
}
```
